```python
import torch

def _softmax(x, axis=-1):
    return torch.softmax(x, dim=axis)
def _gelu(x):
    return torch.nn.functional.gelu(x, approximate="tanh")
def _silu(x):
    return torch.nn.functional.silu(x)
def _sigmoid(x):
    return torch.sigmoid(x)
def _layernorm(x, axis=-1, eps=1e-5):
    m = x.mean(dim=axis, keepdim=True)
    v = x.var(dim=axis, keepdim=True, unbiased=False)
    return (x - m) / torch.sqrt(v + eps)
def _scatter_add(tgt, idx, src, axis=0):
    return tgt.clone().index_add_(axis, idx, src)
def _segment_sum(src, seg, n):
    out = torch.zeros((n,) + src.shape[1:], dtype=src.dtype)
    return out.index_add_(0, seg, src)
def _pad(x, pw):
    flat = tuple(v for pair in reversed(pw) for v in pair)
    return torch.nn.functional.pad(x, flat)

kernel_name = 'gated_mix__ssm_conv_s5__dense_activation_relu__prompt'

def setup_inputs():

    _w = (lambda a: (lambda t: t.to(torch.bfloat16) if t.is_floating_point() else t)(torch.as_tensor(a)))
    def _A_setup():
        B, S, D = 1, 2048, 1024
        P = D
        Lambda_re = -0.5 * (lambda _x: torch.exp(torch.as_tensor(_x)))((lambda *s: torch.randn(*s, dtype=torch.bfloat16) * 0.8)(P))
        Lambda_im = (lambda *s: torch.randn(*s, dtype=torch.bfloat16) * 0.8)(P) * 1.0
        B_re = (lambda *s: torch.randn(*s, dtype=torch.bfloat16) * 0.8)(P, D) * (D ** -0.5)
        B_im = (lambda *s: torch.randn(*s, dtype=torch.bfloat16) * 0.8)(P, D) * (D ** -0.5)
        C_re = (lambda *s: torch.randn(*s, dtype=torch.bfloat16) * 0.8)(D, P) * (P ** -0.5)
        C_im = (lambda *s: torch.randn(*s, dtype=torch.bfloat16) * 0.8)(D, P) * (P ** -0.5)
        log_dt = (lambda *s: torch.randn(*s, dtype=torch.bfloat16) * 0.8)(P) * 0.3 - 2.0
        Dskip = (lambda *s: torch.randn(*s, dtype=torch.bfloat16) * 0.8)(D)
        return {
            "x": _w((lambda *s: torch.randn(*s, dtype=torch.bfloat16) * 0.05)(B, S, D)),
            "Lambda_re": _w(Lambda_re),
            "Lambda_im": _w(Lambda_im),
            "B_re": _w(B_re),
            "B_im": _w(B_im),
            "C_re": _w(C_re),
            "C_im": _w(C_im),
            "log_dt": _w(log_dt),
            "Dskip": _w(Dskip),
        }
    _A_in = _A_setup()

    def _B_setup():
        B, S, D, Dff = 1, 2048, 1024, 3584
        return {
            "x": _w((lambda *s: torch.randn(*s, dtype=torch.bfloat16) * 0.05)(B, S, D)),
            "w1": _w((lambda *s: torch.randn(*s, dtype=torch.bfloat16) * 0.05)(D, Dff)),
            "w2": _w((lambda *s: torch.randn(*s, dtype=torch.bfloat16) * 0.05)(Dff, D)),
        }
    _B_in = _B_setup()

    return {
        "A_x": _A_in["x"],
        "A_Lambda_re": _A_in["Lambda_re"],
        "A_Lambda_im": _A_in["Lambda_im"],
        "A_B_re": _A_in["B_re"],
        "A_B_im": _A_in["B_im"],
        "A_C_re": _A_in["C_re"],
        "A_C_im": _A_in["C_im"],
        "A_log_dt": _A_in["log_dt"],
        "A_Dskip": _A_in["Dskip"],
        "B_x": _B_in["x"],
        "B_w1": _B_in["w1"],
        "B_w2": _B_in["w2"],
        "gate_w": _w((lambda *s: torch.randn(*s, dtype=torch.bfloat16) * 0.05)(1024) * 16.0),
    }

def reference(A_x, A_Lambda_re, A_Lambda_im, A_B_re, A_B_im, A_C_re, A_C_im, A_log_dt, A_Dskip, B_x, B_w1, B_w2, gate_w):
    def _A_ref(x, Lambda_re, Lambda_im, B_re, B_im, C_re, C_im, log_dt, Dskip):
        Bsz, L, H = x.shape
        Lam = Lambda_re + 1j * Lambda_im
        Bmat = B_re + 1j * B_im
        Cmat = C_re + 1j * C_im
        dt = torch.exp(log_dt)
        Lam_bar = torch.exp(dt * Lam)
        B_bar = ((Lam_bar - 1.0) / Lam)[:, None] * Bmat
        Bu = torch.einsum("bld,pd->blp", x + 0j, B_bar)
        h = torch.zeros_like(Bu[:, 0, :])
        hs = []
        for t in range(L):
            h = Lam_bar[None, :] * h + Bu[:, t, :]
            hs.append(h)
        hseq = torch.stack(hs, 1)
        y = 2.0 * torch.einsum("blp,dp->bld", hseq, Cmat).real + x * Dskip[None, None, :]
        return y

    def _B_ref(x, w1, w2):
        h = torch.einsum("bsd,df->bsf", x, w1)
        zero = torch.zeros_like(h)
        h = torch.maximum(h, zero)
        return torch.einsum("bsf,fd->bsd", h, w2)

    x = A_x
    g = _sigmoid((x * gate_w).sum(-1, keepdims=True))
    a = _A_ref(x, A_Lambda_re, A_Lambda_im, A_B_re, A_B_im, A_C_re, A_C_im, A_log_dt, A_Dskip)
    b = _B_ref(x, B_w1, B_w2)
    return g * a + (1 - g) * b
```

```cpp
#include <cuda_runtime.h>
#include <cuda_bf16.h>
#include <cuda.h>
#include <stdint.h>
#include <type_traits>

namespace {

constexpr int SEQ = 2048, DM = 1024, PCH = 1024, DFF = 3584;
constexpr int A_BYTES = 16384;
constexpr int NST1 = 4, ST1_BYTES = 49152;
constexpr int NST2 = 7, ST2_BYTES = 32768;
constexpr int NKB = 88;
constexpr int KB_F1 = 0, KB_F2 = 32, KB_S = 56;
constexpr int NSTEP1 = 76;
constexpr int POLL_NS = 250;
constexpr int PACE = 120;
constexpr int PACE2 = 500;
constexpr int NCTA = 128;
constexpr int NTHREADS = 384;
constexpr long long SPIN_LIMIT = 2000000000ll;

constexpr int SM_STG = NST1 * ST1_BYTES;
constexpr int SM_BAR = SM_STG + 32768;
constexpr int SM_G = SM_BAR + 1024;
constexpr int SM_TOTAL = SM_G + 1024;
constexpr int SMEM_BYTES = SM_TOTAL + 1024;

constexpr int BAR_FULL1 = 0, BAR_EMPTY1 = 4, BAR_STGDEAD = 8, BAR_FULL2 = 9, BAR_EMPTY2 = 16, BAR_G = 23, BAR_LAST = 24,
              BAR_USTORED = 25, BAR_LAG = 26, BAR_XS = 27, BAR_OFREE = 28, BAR_SCANDONE = 29, BAR_SCANLD = 30  ,
              BAR_XSENT = 38, BAR_XREADY = 39, BAR_LAST1 = 40, BAR_XS1 = 41, BAR_DEP = 42  , BAR_STGFULL = 66  ,
              BAR_STGFREE = 90  ;

__device__ __align__(1024) unsigned char g_H[16 * NKB * A_BYTES];
__device__ __align__(1024) float4 g_agg[16 * 512];
__device__ __align__(1024) float g_gate[SEQ];
__device__ __align__(256) unsigned g_flagG[16 * 64];
__device__ __align__(256) unsigned g_flagAgg[16 * 64];
__device__ __align__(256) unsigned g_flagH[16 * 64];
__device__ __align__(256) unsigned g_flagX[NCTA * 32];
__device__ unsigned g_epoch;
__device__ unsigned g_done;

#define BAIL() asm volatile("exit;")
__device__ __forceinline__ uint32_t smem_u32(const void* p) { return (uint32_t)__cvta_generic_to_shared(p); }
__device__ __forceinline__ uint64_t add32(const void* p, uint32_t off) {
  uint32_t lo, hi;
  asm("mov.b64 {%0, %1}, %2;" : "=r"(lo), "=r"(hi) : "l"(p));
  uint64_t r;
  asm("{\n.reg .u32 a, b;\nadd.cc.u32 a, %1, %3;\naddc.u32 b, %2, 0;\nmov.b64 %0, {a, b};\n}\n" : "=l"(r) : "r"(lo), "r"(hi), "r"(off));
  return r;
}
__device__ __forceinline__ uint64_t mk64(uint32_t lo, uint32_t hi) {
  uint64_t r;
  asm("mov.b64 %0, {%1, %2};" : "=l"(r) : "r"(lo), "r"(hi));
  return r;
}

__device__ __forceinline__ void mbar_init(uint32_t bar, uint32_t count) {
  asm volatile("mbarrier.init.shared::cta.b64 [%0], %1;" ::"r"(bar), "r"(count) : "memory");
}
__device__ __forceinline__ void mbar_arrive(uint32_t bar) {
  asm volatile("mbarrier.arrive.shared::cta.b64 _, [%0];" ::"r"(bar) : "memory");
}
__device__ __forceinline__ void mbar_arrive_cl(uint32_t bar_cluster) {
  asm volatile("mbarrier.arrive.shared::cluster.b64 _, [%0];" ::"r"(bar_cluster) : "memory");
}
__device__ __forceinline__ void mbar_expect_tx(uint32_t bar, uint32_t bytes) {
  asm volatile("mbarrier.arrive.expect_tx.shared::cta.b64 _, [%0], %1;" ::"r"(bar), "r"(bytes) : "memory");
}
__device__ __forceinline__ bool mbar_try(uint32_t bar, uint32_t parity) {
  uint32_t ok;
  asm volatile("{\n.reg .pred p;\nmbarrier.try_wait.parity.shared::cta.b64 p, [%1], %2;\nselp.u32 %0, 1, 0, p;\n}\n"
               : "=r"(ok) : "r"(bar), "r"(parity) : "memory");
  return ok != 0;
}
__device__ __forceinline__ bool mbar_test(uint32_t bar, uint32_t parity) {
  uint32_t ok;
  asm volatile("{\n.reg .pred p;\nmbarrier.test_wait.parity.shared::cta.b64 p, [%1], %2;\nselp.u32 %0, 1, 0, p;\n}\n"
               : "=r"(ok) : "r"(bar), "r"(parity) : "memory");
  return ok != 0;
}
__device__ __forceinline__ void mbar_wait(uint32_t bar, uint32_t parity) {
  uint32_t tries = 0;
  while (!mbar_try(bar, parity)) { if (++tries == (1u << 18)) BAIL(); }
}
__device__ __forceinline__ uint32_t mapa(uint32_t addr, uint32_t rank) {
  uint32_t r;
  asm volatile("mapa.shared::cluster.u32 %0, %1, %2;" : "=r"(r) : "r"(addr), "r"(rank));
  return r;
}
__device__ __forceinline__ bool elect_one() {
  uint32_t el;
  asm volatile("{\n.reg .pred p;\nelect.sync _|p, 0xffffffff;\nselp.u32 %0, 1, 0, p;\n}\n" : "=r"(el));
  return el != 0;
}
__device__ __forceinline__ unsigned ld_acquire(const unsigned* p) {
  unsigned v;
  asm volatile("ld.acquire.gpu.global.u32 %0, [%1];" : "=r"(v) : "l"(p) : "memory");
  return v;
}
__device__ __forceinline__ unsigned ld_relaxed(const unsigned* p) {
  unsigned v;
  asm volatile("ld.relaxed.gpu.global.u32 %0, [%1];" : "=r"(v) : "l"(p) : "memory");
  return v;
}
__device__ __forceinline__ void st_release(unsigned* p, unsigned v) {
  asm volatile("st.release.gpu.global.u32 [%0], %1;" ::"l"(p), "r"(v) : "memory");
}
__device__ __forceinline__ void red_release_add(unsigned* p, unsigned v) {
  asm volatile("red.release.gpu.global.add.u32 [%0], %1;" ::"l"(p), "r"(v) : "memory");
}
__device__ __forceinline__ void fence_proxy_async() {
  asm volatile("fence.proxy.async.global;" ::: "memory");
}
__device__ __forceinline__ void wait_flag(const unsigned* p, unsigned target) {
  const long long t0 = clock64();
  while ((int)(ld_relaxed(p) - target) < 0) { __nanosleep(POLL_NS); if (clock64() - t0 > SPIN_LIMIT) BAIL(); }
  (void)ld_acquire(p);
}

__device__ __forceinline__ void tma_2d(uint32_t dst, const CUtensorMap* map, int c0, int c1, uint32_t bar) {
  asm volatile("cp.async.bulk.tensor.2d.shared::cluster.global.mbarrier::complete_tx::bytes [%0], [%1, {%3, %4}], [%2];"
               ::"r"(dst), "l"(map), "r"(bar), "r"(c0), "r"(c1) : "memory");
}
__device__ __forceinline__ void tma_2d_mc(uint32_t dst, const CUtensorMap* map, int c0, int c1, uint32_t bar) {
  asm volatile("cp.async.bulk.tensor.2d.shared::cluster.global.mbarrier::complete_tx::bytes.multicast::cluster [%0], [%1, {%3, %4}], [%2], %5;"
               ::"r"(dst), "l"(map), "r"(bar), "r"(c0), "r"(c1), "h"((uint16_t)3) : "memory");
}
__device__ __forceinline__ void tma_3d(uint32_t dst, const CUtensorMap* map, int c0, int c1, int c2, uint32_t bar) {
  asm volatile("cp.async.bulk.tensor.3d.shared::cluster.global.mbarrier::complete_tx::bytes [%0], [%1, {%3, %4, %5}], [%2];"
               ::"r"(dst), "l"(map), "r"(bar), "r"(c0), "r"(c1), "r"(c2) : "memory");
}
__device__ __forceinline__ void tma_3d_mc(uint32_t dst, const CUtensorMap* map, int c0, int c1, int c2, uint32_t bar) {
  asm volatile("cp.async.bulk.tensor.3d.shared::cluster.global.mbarrier::complete_tx::bytes.multicast::cluster [%0], [%1, {%3, %4, %5}], [%2], %6;"
               ::"r"(dst), "l"(map), "r"(bar), "r"(c0), "r"(c1), "r"(c2), "h"((uint16_t)3) : "memory");
}
__device__ __forceinline__ void tma_store_2d(const CUtensorMap* map, uint32_t src, int c0, int c1) {
  asm volatile("cp.async.bulk.tensor.2d.global.shared::cta.bulk_group [%0, {%2, %3}], [%1];"
               ::"l"(map), "r"(src), "r"(c0), "r"(c1) : "memory");
}
__device__ __forceinline__ uint32_t lds32(uint32_t addr) {
  uint32_t v;
  asm volatile("ld.shared.b32 %0, [%1];" : "=r"(v) : "r"(addr) : "memory");
  return v;
}
__device__ __forceinline__ void prefetch_map(const CUtensorMap* map) {
  asm volatile("prefetch.tensormap [%0];" ::"l"(map) : "memory");
}
__device__ __forceinline__ void wgmma_fence() { asm volatile("wgmma.fence.sync.aligned;" ::: "memory"); }
__device__ __forceinline__ void wgmma_commit() { asm volatile("wgmma.commit_group.sync.aligned;" ::: "memory"); }
template <int N> __device__ __forceinline__ void wgmma_wait() { asm volatile("wgmma.wait_group.sync.aligned %0;" ::"n"(N) : "memory"); }

__device__ __forceinline__ uint32_t pack_bf16(float lo, float hi) {
  uint32_t r;
  asm("cvt.rn.bf16x2.f32 %0, %1, %2;" : "=r"(r) : "f"(hi), "f"(lo));
  return r;
}
__device__ __forceinline__ float bf_lo(uint32_t v) { return __uint_as_float(v << 16); }
__device__ __forceinline__ float bf_hi(uint32_t v) { return __uint_as_float(v & 0xffff0000u); }
__device__ __forceinline__ float round_bf16(float v) { return __bfloat162float(__float2bfloat16_rn(v)); }

__device__ __forceinline__ void wgmma_n256_kmaj(float (&d)[128], uint64_t da, uint64_t db, int scale_d) {
  asm volatile("{\n.reg .pred p;\nsetp.ne.b32 p, %130, 0;\n"
    "wgmma.mma_async.sync.aligned.m64n256k16.f32.bf16.bf16 "
    "{%0, %1, %2, %3, %4, %5, %6, %7, %8, %9, %10, %11, %12, %13, %14, %15, "
    "%16, %17, %18, %19, %20, %21, %22, %23, %24, %25, %26, %27, %28, %29, %30, %31, "
    "%32, %33, %34, %35, %36, %37, %38, %39, %40, %41, %42, %43, %44, %45, %46, %47, "
    "%48, %49, %50, %51, %52, %53, %54, %55, %56, %57, %58, %59, %60, %61, %62, %63, "
    "%64, %65, %66, %67, %68, %69, %70, %71, %72, %73, %74, %75, %76, %77, %78, %79, "
    "%80, %81, %82, %83, %84, %85, %86, %87, %88, %89, %90, %91, %92, %93, %94, %95, "
    "%96, %97, %98, %99, %100, %101, %102, %103, %104, %105, %106, %107, %108, %109, %110, %111, "
    "%112, %113, %114, %115, %116, %117, %118, %119, %120, %121, %122, %123, %124, %125, %126, %127}, "
    "%128, %129, p, 1, 1, 0, 0;\n}\n"
    : "+f"(d[0]), "+f"(d[1]), "+f"(d[2]), "+f"(d[3]), "+f"(d[4]), "+f"(d[5]), "+f"(d[6]), "+f"(d[7]),
      "+f"(d[8]), "+f"(d[9]), "+f"(d[10]), "+f"(d[11]), "+f"(d[12]), "+f"(d[13]), "+f"(d[14]), "+f"(d[15]),
      "+f"(d[16]), "+f"(d[17]), "+f"(d[18]), "+f"(d[19]), "+f"(d[20]), "+f"(d[21]), "+f"(d[22]), "+f"(d[23]),
      "+f"(d[24]), "+f"(d[25]), "+f"(d[26]), "+f"(d[27]), "+f"(d[28]), "+f"(d[29]), "+f"(d[30]), "+f"(d[31]),
      "+f"(d[32]), "+f"(d[33]), "+f"(d[34]), "+f"(d[35]), "+f"(d[36]), "+f"(d[37]), "+f"(d[38]), "+f"(d[39]),
      "+f"(d[40]), "+f"(d[41]), "+f"(d[42]), "+f"(d[43]), "+f"(d[44]), "+f"(d[45]), "+f"(d[46]), "+f"(d[47]),
      "+f"(d[48]), "+f"(d[49]), "+f"(d[50]), "+f"(d[51]), "+f"(d[52]), "+f"(d[53]), "+f"(d[54]), "+f"(d[55]),
      "+f"(d[56]), "+f"(d[57]), "+f"(d[58]), "+f"(d[59]), "+f"(d[60]), "+f"(d[61]), "+f"(d[62]), "+f"(d[63]),
      "+f"(d[64]), "+f"(d[65]), "+f"(d[66]), "+f"(d[67]), "+f"(d[68]), "+f"(d[69]), "+f"(d[70]), "+f"(d[71]),
      "+f"(d[72]), "+f"(d[73]), "+f"(d[74]), "+f"(d[75]), "+f"(d[76]), "+f"(d[77]), "+f"(d[78]), "+f"(d[79]),
      "+f"(d[80]), "+f"(d[81]), "+f"(d[82]), "+f"(d[83]), "+f"(d[84]), "+f"(d[85]), "+f"(d[86]), "+f"(d[87]),
      "+f"(d[88]), "+f"(d[89]), "+f"(d[90]), "+f"(d[91]), "+f"(d[92]), "+f"(d[93]), "+f"(d[94]), "+f"(d[95]),
      "+f"(d[96]), "+f"(d[97]), "+f"(d[98]), "+f"(d[99]), "+f"(d[100]), "+f"(d[101]), "+f"(d[102]), "+f"(d[103]),
      "+f"(d[104]), "+f"(d[105]), "+f"(d[106]), "+f"(d[107]), "+f"(d[108]), "+f"(d[109]), "+f"(d[110]), "+f"(d[111]),
      "+f"(d[112]), "+f"(d[113]), "+f"(d[114]), "+f"(d[115]), "+f"(d[116]), "+f"(d[117]), "+f"(d[118]), "+f"(d[119]),
      "+f"(d[120]), "+f"(d[121]), "+f"(d[122]), "+f"(d[123]), "+f"(d[124]), "+f"(d[125]), "+f"(d[126]), "+f"(d[127])
    : "l"(da), "l"(db), "r"(scale_d));
}
__device__ __forceinline__ void wgmma_n256_nmaj(float (&d)[128], uint64_t da, uint64_t db, int scale_d) {
  asm volatile("{\n.reg .pred p;\nsetp.ne.b32 p, %130, 0;\n"
    "wgmma.mma_async.sync.aligned.m64n256k16.f32.bf16.bf16 "
    "{%0, %1, %2, %3, %4, %5, %6, %7, %8, %9, %10, %11, %12, %13, %14, %15, "
    "%16, %17, %18, %19, %20, %21, %22, %23, %24, %25, %26, %27, %28, %29, %30, %31, "
    "%32, %33, %34, %35, %36, %37, %38, %39, %40, %41, %42, %43, %44, %45, %46, %47, "
    "%48, %49, %50, %51, %52, %53, %54, %55, %56, %57, %58, %59, %60, %61, %62, %63, "
    "%64, %65, %66, %67, %68, %69, %70, %71, %72, %73, %74, %75, %76, %77, %78, %79, "
    "%80, %81, %82, %83, %84, %85, %86, %87, %88, %89, %90, %91, %92, %93, %94, %95, "
    "%96, %97, %98, %99, %100, %101, %102, %103, %104, %105, %106, %107, %108, %109, %110, %111, "
    "%112, %113, %114, %115, %116, %117, %118, %119, %120, %121, %122, %123, %124, %125, %126, %127}, "
    "%128, %129, p, 1, 1, 0, 1;\n}\n"
    : "+f"(d[0]), "+f"(d[1]), "+f"(d[2]), "+f"(d[3]), "+f"(d[4]), "+f"(d[5]), "+f"(d[6]), "+f"(d[7]),
      "+f"(d[8]), "+f"(d[9]), "+f"(d[10]), "+f"(d[11]), "+f"(d[12]), "+f"(d[13]), "+f"(d[14]), "+f"(d[15]),
      "+f"(d[16]), "+f"(d[17]), "+f"(d[18]), "+f"(d[19]), "+f"(d[20]), "+f"(d[21]), "+f"(d[22]), "+f"(d[23]),
      "+f"(d[24]), "+f"(d[25]), "+f"(d[26]), "+f"(d[27]), "+f"(d[28]), "+f"(d[29]), "+f"(d[30]), "+f"(d[31]),
      "+f"(d[32]), "+f"(d[33]), "+f"(d[34]), "+f"(d[35]), "+f"(d[36]), "+f"(d[37]), "+f"(d[38]), "+f"(d[39]),
      "+f"(d[40]), "+f"(d[41]), "+f"(d[42]), "+f"(d[43]), "+f"(d[44]), "+f"(d[45]), "+f"(d[46]), "+f"(d[47]),
      "+f"(d[48]), "+f"(d[49]), "+f"(d[50]), "+f"(d[51]), "+f"(d[52]), "+f"(d[53]), "+f"(d[54]), "+f"(d[55]),
      "+f"(d[56]), "+f"(d[57]), "+f"(d[58]), "+f"(d[59]), "+f"(d[60]), "+f"(d[61]), "+f"(d[62]), "+f"(d[63]),
      "+f"(d[64]), "+f"(d[65]), "+f"(d[66]), "+f"(d[67]), "+f"(d[68]), "+f"(d[69]), "+f"(d[70]), "+f"(d[71]),
      "+f"(d[72]), "+f"(d[73]), "+f"(d[74]), "+f"(d[75]), "+f"(d[76]), "+f"(d[77]), "+f"(d[78]), "+f"(d[79]),
      "+f"(d[80]), "+f"(d[81]), "+f"(d[82]), "+f"(d[83]), "+f"(d[84]), "+f"(d[85]), "+f"(d[86]), "+f"(d[87]),
      "+f"(d[88]), "+f"(d[89]), "+f"(d[90]), "+f"(d[91]), "+f"(d[92]), "+f"(d[93]), "+f"(d[94]), "+f"(d[95]),
      "+f"(d[96]), "+f"(d[97]), "+f"(d[98]), "+f"(d[99]), "+f"(d[100]), "+f"(d[101]), "+f"(d[102]), "+f"(d[103]),
      "+f"(d[104]), "+f"(d[105]), "+f"(d[106]), "+f"(d[107]), "+f"(d[108]), "+f"(d[109]), "+f"(d[110]), "+f"(d[111]),
      "+f"(d[112]), "+f"(d[113]), "+f"(d[114]), "+f"(d[115]), "+f"(d[116]), "+f"(d[117]), "+f"(d[118]), "+f"(d[119]),
      "+f"(d[120]), "+f"(d[121]), "+f"(d[122]), "+f"(d[123]), "+f"(d[124]), "+f"(d[125]), "+f"(d[126]), "+f"(d[127])
    : "l"(da), "l"(db), "r"(scale_d));
}
__device__ __forceinline__ void wgmma_n192_nmaj(float (&d)[128], uint64_t da, uint64_t db, int scale_d) {
  asm volatile("{\n.reg .pred p;\nsetp.ne.b32 p, %98, 0;\n"
    "wgmma.mma_async.sync.aligned.m64n192k16.f32.bf16.bf16 "
    "{%0, %1, %2, %3, %4, %5, %6, %7, %8, %9, %10, %11, %12, %13, %14, %15, "
    "%16, %17, %18, %19, %20, %21, %22, %23, %24, %25, %26, %27, %28, %29, %30, %31, "
    "%32, %33, %34, %35, %36, %37, %38, %39, %40, %41, %42, %43, %44, %45, %46, %47, "
    "%48, %49, %50, %51, %52, %53, %54, %55, %56, %57, %58, %59, %60, %61, %62, %63, "
    "%64, %65, %66, %67, %68, %69, %70, %71, %72, %73, %74, %75, %76, %77, %78, %79, "
    "%80, %81, %82, %83, %84, %85, %86, %87, %88, %89, %90, %91, %92, %93, %94, %95}, "
    "%96, %97, p, 1, 1, 0, 1;\n}\n"
    : "+f"(d[0]), "+f"(d[1]), "+f"(d[2]), "+f"(d[3]), "+f"(d[4]), "+f"(d[5]), "+f"(d[6]), "+f"(d[7]),
      "+f"(d[8]), "+f"(d[9]), "+f"(d[10]), "+f"(d[11]), "+f"(d[12]), "+f"(d[13]), "+f"(d[14]), "+f"(d[15]),
      "+f"(d[16]), "+f"(d[17]), "+f"(d[18]), "+f"(d[19]), "+f"(d[20]), "+f"(d[21]), "+f"(d[22]), "+f"(d[23]),
      "+f"(d[24]), "+f"(d[25]), "+f"(d[26]), "+f"(d[27]), "+f"(d[28]), "+f"(d[29]), "+f"(d[30]), "+f"(d[31]),
      "+f"(d[32]), "+f"(d[33]), "+f"(d[34]), "+f"(d[35]), "+f"(d[36]), "+f"(d[37]), "+f"(d[38]), "+f"(d[39]),
      "+f"(d[40]), "+f"(d[41]), "+f"(d[42]), "+f"(d[43]), "+f"(d[44]), "+f"(d[45]), "+f"(d[46]), "+f"(d[47]),
      "+f"(d[48]), "+f"(d[49]), "+f"(d[50]), "+f"(d[51]), "+f"(d[52]), "+f"(d[53]), "+f"(d[54]), "+f"(d[55]),
      "+f"(d[56]), "+f"(d[57]), "+f"(d[58]), "+f"(d[59]), "+f"(d[60]), "+f"(d[61]), "+f"(d[62]), "+f"(d[63]),
      "+f"(d[64]), "+f"(d[65]), "+f"(d[66]), "+f"(d[67]), "+f"(d[68]), "+f"(d[69]), "+f"(d[70]), "+f"(d[71]),
      "+f"(d[72]), "+f"(d[73]), "+f"(d[74]), "+f"(d[75]), "+f"(d[76]), "+f"(d[77]), "+f"(d[78]), "+f"(d[79]),
      "+f"(d[80]), "+f"(d[81]), "+f"(d[82]), "+f"(d[83]), "+f"(d[84]), "+f"(d[85]), "+f"(d[86]), "+f"(d[87]),
      "+f"(d[88]), "+f"(d[89]), "+f"(d[90]), "+f"(d[91]), "+f"(d[92]), "+f"(d[93]), "+f"(d[94]), "+f"(d[95])
    : "l"(da), "l"(db), "r"(scale_d));
}
__device__ __forceinline__ void wgmma_n128_kmaj(float (&d)[128], uint64_t da, uint64_t db, int scale_d) {
  asm volatile("{\n.reg .pred p;\nsetp.ne.b32 p, %66, 0;\n"
    "wgmma.mma_async.sync.aligned.m64n128k16.f32.bf16.bf16 "
    "{%0, %1, %2, %3, %4, %5, %6, %7, %8, %9, %10, %11, %12, %13, %14, %15, "
    "%16, %17, %18, %19, %20, %21, %22, %23, %24, %25, %26, %27, %28, %29, %30, %31, "
    "%32, %33, %34, %35, %36, %37, %38, %39, %40, %41, %42, %43, %44, %45, %46, %47, "
    "%48, %49, %50, %51, %52, %53, %54, %55, %56, %57, %58, %59, %60, %61, %62, %63}, "
    "%64, %65, p, 1, 1, 0, 0;\n}\n"
    : "+f"(d[0]), "+f"(d[1]), "+f"(d[2]), "+f"(d[3]), "+f"(d[4]), "+f"(d[5]), "+f"(d[6]), "+f"(d[7]),
      "+f"(d[8]), "+f"(d[9]), "+f"(d[10]), "+f"(d[11]), "+f"(d[12]), "+f"(d[13]), "+f"(d[14]), "+f"(d[15]),
      "+f"(d[16]), "+f"(d[17]), "+f"(d[18]), "+f"(d[19]), "+f"(d[20]), "+f"(d[21]), "+f"(d[22]), "+f"(d[23]),
      "+f"(d[24]), "+f"(d[25]), "+f"(d[26]), "+f"(d[27]), "+f"(d[28]), "+f"(d[29]), "+f"(d[30]), "+f"(d[31]),
      "+f"(d[32]), "+f"(d[33]), "+f"(d[34]), "+f"(d[35]), "+f"(d[36]), "+f"(d[37]), "+f"(d[38]), "+f"(d[39]),
      "+f"(d[40]), "+f"(d[41]), "+f"(d[42]), "+f"(d[43]), "+f"(d[44]), "+f"(d[45]), "+f"(d[46]), "+f"(d[47]),
      "+f"(d[48]), "+f"(d[49]), "+f"(d[50]), "+f"(d[51]), "+f"(d[52]), "+f"(d[53]), "+f"(d[54]), "+f"(d[55]),
      "+f"(d[56]), "+f"(d[57]), "+f"(d[58]), "+f"(d[59]), "+f"(d[60]), "+f"(d[61]), "+f"(d[62]), "+f"(d[63])
    : "l"(da), "l"(db), "r"(scale_d));
}

constexpr uint32_t DESC_HI = 0x40000040u;
__device__ __forceinline__ uint32_t desc_k(uint32_t addr) { return ((addr & 0x3FFFF) >> 4) | (1u << 16); }
__device__ __forceinline__ uint32_t desc_mn4k(uint32_t addr) { return ((addr & 0x3FFFF) >> 4) | (256u << 16); }
__device__ __forceinline__ uint64_t D(uint32_t lo) { return mk64(lo, DESC_HI); }

__device__ __forceinline__ void stmatrix_x4(uint32_t addr, uint32_t r0, uint32_t r1, uint32_t r2, uint32_t r3) {
  asm volatile("stmatrix.sync.aligned.m8n8.x4.shared.b16 [%0], {%1, %2, %3, %4};" ::"r"(addr), "r"(r0), "r"(r1), "r"(r2), "r"(r3) : "memory");
}

__device__ __forceinline__ uint32_t mul_bf16x2(uint32_t a, uint32_t b) {
  uint32_t r;
  asm("mul.rn.bf16x2 %0, %1, %2;" : "=r"(r) : "r"(a), "r"(b));
  return r;
}
__device__ __forceinline__ float bf_lo_dep(uint32_t v, uint32_t z) { return __uint_as_float(v * 65536u + z); }
__device__ __forceinline__ float bf_hi_dep(uint32_t v, uint32_t z) {
  uint32_t r;
  asm("lop3.b32 %0, %1, 0xffff0000, %2, 0xEA;" : "=r"(r) : "r"(v), "r"(z));
  return __uint_as_float(r);
}

struct Params {
  const __nv_bfloat16 *x, *lam_re, *lam_im, *log_dt, *dskip, *gate_w;
  float* out;
  uint32_t zero;
};

__device__ __forceinline__ void cmad(float& sr, float& si, float lr, float li, float ur, float ui) {
  const float a = fmaf(sr, lr, fmaf(-si, li, ur));
  const float b = fmaf(sr, li, fmaf(si, lr, ui));
  sr = a; si = b;
}

constexpr int NPRE = 2;
constexpr int XSEND = 19;
constexpr int SKIP2 = 25;
constexpr int SKIPAT = 20;
template <bool KNOWN_TOPOLOGY>
__global__ void __cluster_dims__(2, 1, 1) __launch_bounds__(NTHREADS, 1)
fused_kernel(const __grid_constant__ CUtensorMap tm_x, const __grid_constant__ CUtensorMap tm_bre,
             const __grid_constant__ CUtensorMap tm_bim, const __grid_constant__ CUtensorMap tm_w1a,
             const __grid_constant__ CUtensorMap tm_w1b, const __grid_constant__ CUtensorMap tm_w2,
             const __grid_constant__ CUtensorMap tm_cre, const __grid_constant__ CUtensorMap tm_cim,
             const __grid_constant__ CUtensorMap tm_out, const __grid_constant__ CUtensorMap tm_hld,
             const __grid_constant__ CUtensorMap tm_hst, const __grid_constant__ CUtensorMap tm_u, const Params prm) {
  extern __shared__ unsigned char smem_raw[];
  asm volatile("{\n.reg .pred p;\nsetp.eq.u32 p, %3, 0;\n@p prefetch.tensormap [%0];\n@p prefetch.tensormap [%1];\n@p prefetch.tensormap [%2];\n}\n"
               ::"l"(&tm_x), "l"(&tm_bre), "l"(&tm_bim), "r"(threadIdx.x) : "memory");
  const uint32_t sbase = (smem_u32(smem_raw) + 1023u) & ~1023u;
  unsigned char* sgen = smem_raw + (sbase - smem_u32(smem_raw));
  const uint32_t bars = sbase + SM_BAR;
  float* s_g = reinterpret_cast<float*>(sgen + SM_G);

  const int tid = threadIdx.x, lane = tid & 31;
  const int warp = __shfl_sync(0xffffffffu, tid >> 5, 0);
  const int rank = blockIdx.x & 1;
  int cl = blockIdx.x >> 1;
  if (KNOWN_TOPOLOGY) {
    const int q = cl - 36, q7 = (q * 37) >> 8;
    const int r = cl < 4 ? cl : cl < 36 ? (cl - 4) >> 3 : q7;
    const int h = cl < 4 ? 1 : cl < 36 ? 2 * ((cl - 4) & 7) : 2 * (q - 7 * q7) + 3;
    cl = (h >> 1) + 8 * (2 * r + (h & 1));
  }
  const int bid = 2 * cl + rank;
  const int m = 2 * (cl & 7) + rank, j = cl >> 3;
  const int kh = j & 1;
  unsigned char* Hm = g_H + (size_t)m * NKB * A_BYTES;

  if (__builtin_expect(warp == 0, 1)) {
    if (elect_one()) {
#pragma unroll
      for (int s = 0; s < NST1; ++s) mbar_init(bars + 8 * (BAR_FULL1 + s), 1);
      asm volatile("fence.mbarrier_init.release.cluster;" ::: "memory");
#pragma unroll
      for (int it = 0; it < NPRE; ++it) {
        const uint32_t st = sbase + it * ST1_BYTES, fb = bars + 8 * (BAR_FULL1 + it);
        mbar_expect_tx(fb, ST1_BYTES);
        tma_2d(st, &tm_x, it * 64, m * 128, fb);
        tma_2d(st + A_BYTES, &tm_bre, it * 64, j * 128, fb);
        tma_2d(st + A_BYTES + 16384, &tm_bim, it * 64, j * 128, fb);
      }
    }
  }
  asm volatile("" ::: "memory");
  __syncwarp();
  if (warp == 1) {
    if (elect_one()) {
#pragma unroll
      for (int b = BAR_EMPTY1; b < BAR_DEP; ++b)
        mbar_init(bars + 8 * b, (b < BAR_FULL2 || (b >= BAR_EMPTY2 && b < BAR_G)) ? 16 : (b == BAR_LAST || b == BAR_OFREE || b == BAR_LAG || b == BAR_LAST1) ? 4 : b == BAR_XSENT ? 8 : b == BAR_SCANDONE ? 2 : 1);
      asm volatile("fence.mbarrier_init.release.cluster;" ::: "memory");
    }
  } else if (warp >= 2 && warp < 5) {
    if (elect_one()) {
      const uint32_t cnt = warp == 3 ? 4 : 1;
#pragma unroll
      for (int b = 0; b < 24; ++b) mbar_init(bars + 8 * (BAR_DEP + (warp - 2) * 24 + b), cnt);
      asm volatile("fence.mbarrier_init.release.cluster;" ::: "memory");
    }
  }
  __syncwarp();
  asm volatile("barrier.cluster.arrive.relaxed.aligned;\nbarrier.cluster.wait.aligned;" ::: "memory");

  if (warp < 4) {
    asm volatile("setmaxnreg.dec.sync.aligned.u32 72;");
    if (warp == 0) {
      uint32_t dep = 0;
#pragma unroll 1
      for (int n = NPRE; n < NSTEP1; ++n) {
        const uint32_t stage = n & 3;
        const uint32_t st = sbase + stage * ST1_BYTES, fb = bars + 8 * (BAR_FULL1 + stage);
        if (n >= 48 && (n < 64 ? (n & 3) == 0 : ((0x249u >> (n - 64)) & 1) != 0)) { mbar_wait(bars + 8 * (BAR_DEP + dep), 0); ++dep; }
        mbar_wait(bars + 8 * (BAR_EMPTY1 + stage), ((n >> 2) & 1) ^ 1);
        if (elect_one()) {
          const int k0 = (n & 15) * 64;
          mbar_expect_tx(fb, (n >> 4) == 2 ? A_BYTES + 24576 : ST1_BYTES);
          if (n < 48) {
            if (n < 16) tma_2d_mc(st + A_BYTES + rank * 16384, rank ? &tm_bim : &tm_bre, k0, j * 128, fb);
            else if (n < 32) tma_3d_mc(st + A_BYTES + rank * 16384, &tm_w1a, 0, k0 + rank * 32, 4 * j, fb);
            else tma_3d_mc(st + A_BYTES + rank * 12288, &tm_w1b, 0, k0 + rank * 32, 32 + 3 * j, fb);
            tma_2d(st, &tm_x, k0, m * 128, fb);
          } else {
            const int kb = n < 64 ? 16 * kh + n - 48 : KB_F2 + 12 * kh + n - 64;
            tma_3d_mc(st + A_BYTES + rank * 16384, &tm_w2, 0, kb * 64 + rank * 32, 2 * (j ^ 1), fb);
            tma_3d_mc(st + A_BYTES + rank * 16384 + 8192, &tm_w2, 0, kb * 64 + rank * 32, 2 * j, fb);
            tma_2d(st, &tm_hld, 0, (m * NKB + kb) * 128, fb);
          }
        }
        __syncwarp();
      }
      uint32_t slot = 0, ph = 1;
#pragma unroll 1
      for (int i = 0; i < 32; ++i) {
        const uint32_t st = sbase + slot * ST2_BYTES, fb = bars + 8 * (BAR_FULL2 + slot);
        if ((i & 3) == 0) { mbar_wait(bars + 8 * (BAR_DEP + dep), 0); ++dep; }
        if (i < NST2) mbar_wait(bars + 8 * (BAR_EMPTY1 + ((0x4332110u >> (4 * i)) & 15)), 0);
        else mbar_wait(bars + 8 * (BAR_EMPTY2 + slot), ph);
        if (elect_one()) {
          mbar_expect_tx(fb, ST2_BYTES);
          tma_2d_mc(st + A_BYTES + rank * 8192, (i & 2) ? &tm_cim : &tm_cre, (i >> 2) * 128 + (i & 1) * 64, j * 128 + rank * 64, fb);
          tma_2d(st, &tm_hld, 0, (m * NKB + KB_S + i) * 128, fb);
        }
        __syncwarp();
        if (++slot == NST2) { slot = 0; ph ^= 1; }
      }
    } else if (warp == 3) {
      const unsigned ep = ld_relaxed(&g_epoch);
      if (lane == 0) {
        prefetch_map(&tm_w1a); prefetch_map(&tm_w1b); prefetch_map(&tm_w2); prefetch_map(&tm_cre); prefetch_map(&tm_cim);
        prefetch_map(&tm_out); prefetch_map(&tm_hld); prefetch_map(&tm_hst); prefetch_map(&tm_u);
      }
      const unsigned* fp = &g_flagH[m * 64 + (lane < 8 ? (lane >> 2) * 8 + 4 * kh + (lane & 3) : 8 + lane)];
      unsigned* myflag = &g_flagH[m * 64 + j];
      const float* gsrc = g_gate + m * 128 + lane * 4;
      const uint2 dsk = __ldg(reinterpret_cast<const uint2*>(prm.dskip + (j ^ 1) * 128) + lane);
      const unsigned target = lane >= 8 ? (ep + 1) * 2 : ep + 1;
      bool pending = lane < 16;
#pragma unroll 1
      for (int f = 0; f < 3; ++f) {
        const uint32_t kb0 = f == 0 ? KB_S + 4 * j : f == 1 ? KB_F1 + 4 * j : KB_F2 + 3 * j;
        {
          const uint32_t pace = f == 2 ? PACE2 : PACE;
          uint32_t tnext = clock();
          uint32_t lastbar = 0;
#pragma unroll 1
          for (uint32_t ii = 0; ii < (f == 2 ? 6 : 8); ++ii) {
            const uint32_t p = f == 0 ? (ii & 3) : (ii >> 1), w = f == 0 ? (ii >> 2) : (ii & 1);
            const uint32_t i = 4 * w + p;
            if (!__all_sync(0xffffffffu, mbar_test(bars + 8 * (BAR_STGFULL + 8 * f + i), 0))) {
              if (lastbar && lane == 0) { asm volatile("cp.async.bulk.wait_group.read 0;" ::: "memory"); mbar_arrive(lastbar); }
              lastbar = 0;
              mbar_wait(bars + 8 * (BAR_STGFULL + 8 * f + i), 0);
            }
            const int drow = (m * NKB + kb0 + p) * 128 + w * 64;
            const uint32_t src = sbase + SM_STG + (f == 0 ? p : w) * 8192;
            while ((int)(clock() - tnext) < 0) {}
            tnext = clock() + pace;
            if (lane == 0) {
              asm volatile("fence.proxy.async.shared::cta;" ::: "memory");
              tma_store_2d(&tm_hst, src, 0, drow);
            }
            while ((int)(clock() - tnext) < 0) {}
            tnext += pace;
            if (lane == 0) {
              tma_store_2d(&tm_hst, src + 4096, 0, drow + 32);
              asm volatile("cp.async.bulk.commit_group;\ncp.async.bulk.wait_group.read 1;" ::: "memory");
              if (lastbar) mbar_arrive(lastbar);
            }
            __syncwarp();
            lastbar = bars + 8 * (BAR_STGFREE + 8 * f + i);
          }
          if (lane == 0) {
            asm volatile("cp.async.bulk.wait_group.read 0;" ::: "memory");
            mbar_arrive(lastbar);
            asm volatile("cp.async.bulk.wait_group 0;" ::: "memory");
            if (f == 0) {
              mbar_arrive(bars + 8 * BAR_USTORED);
            } else {
              fence_proxy_async();
              st_release(myflag + 8 * (f - 1), ep + 1);
            }
            if (f == 2) {
              mbar_expect_tx(bars + 8 * BAR_XS, 16384);
              tma_2d(sbase + SM_STG, &tm_x, (j ^ 1) * 128, m * 128, bars + 8 * BAR_XS);
            }
          }
        }
        __syncwarp();
        if (f == 0) {
          if (lane == 0) wait_flag(&g_flagG[m * 64], (ep + 1) * 16);
          __syncwarp();
          {
            float4 v;
            asm volatile("ld.relaxed.gpu.global.v4.f32 {%0, %1, %2, %3}, [%4];" : "=f"(v.x), "=f"(v.y), "=f"(v.z), "=f"(v.w)
                         : "l"(gsrc) : "memory");
            reinterpret_cast<float4*>(s_g)[lane] = v;
            reinterpret_cast<uint2*>(s_g + 128)[lane] = dsk;
          }
          __syncwarp();
          if (lane == 0) mbar_arrive(bars + 8 * BAR_G);
        }
        const long long t0 = clock64();
        while (__any_sync(0xffffffffu, pending && (f == 2 || (f == 1 && lane < 4)))) {
          if (pending && (int)(ld_relaxed(fp) - target) >= 0) {
            (void)ld_acquire(fp);
            mbar_arrive(bars + 8 * (BAR_DEP + lane));
            pending = false;
          }
          __nanosleep(POLL_NS);
          if (clock64() - t0 > SPIN_LIMIT) BAIL();
        }
      }
      mbar_wait(bars + 8 * BAR_XSENT, 0);
      if (lane == 0) {
        st_release(&g_flagX[bid * 32], ep + 1);
        wait_flag(&g_flagX[(bid ^ 16) * 32], ep + 1);
        mbar_arrive(bars + 8 * BAR_XREADY);
      }
    } else {
      const int blk = warp - 1;
      const unsigned ep = ld_relaxed(&g_epoch);
      const int ch = j * 128 + blk * 64 + 2 * lane;
      float lr[2], li[2], cr[2], ci[2], pr[2], pi[2];
      const uint32_t wre = __ldg(reinterpret_cast<const uint32_t*>(prm.lam_re + ch));
      const uint32_t wim = __ldg(reinterpret_cast<const uint32_t*>(prm.lam_im + ch));
      const uint32_t wdt = __ldg(reinterpret_cast<const uint32_t*>(prm.log_dt + ch));
#pragma unroll 1
      for (int e = 0; e < 2; ++e) {
        const float a = e ? bf_hi(wre) : bf_lo(wre), b = e ? bf_hi(wim) : bf_lo(wim);
        const float dt = round_bf16(expf(e ? bf_hi(wdt) : bf_lo(wdt)));
        const float ex = expf(dt * a);
        float sn, cs;
        sincospif(dt * b * 0.31830988618379067f, &sn, &cs);
        const float vr = ex * cs, vi = ex * sn;
        const float nr = vr - 1.f, ni = vi;
        float qr, qi;
        if (fabsf(a) >= fabsf(b)) { const float t = b / a, den = a + b * t; qr = (nr + ni * t) / den; qi = (ni - nr * t) / den; }
        else { const float t = a / b, den = a * t + b; qr = (nr * t + ni) / den; qi = (ni * t - nr) / den; }
        float xr = vr, xi = vi;
#pragma unroll
        for (int s = 0; s < 7; ++s) { const float t = xr * xr - xi * xi; xi = 2.f * xr * xi; xr = t; }
        if (e == 0) { lr[0] = vr; li[0] = vi; cr[0] = 2.f * qr; ci[0] = 2.f * qi; pr[0] = xr; pi[0] = xi; }
        else        { lr[1] = vr; li[1] = vi; cr[1] = 2.f * qr; ci[1] = 2.f * qi; pr[1] = xr; pi[1] = xi; }
      }
      {
        uint4 gw[4];
        const int row0 = m * 128 + j * 16 + blk * 8;
        const uint4* xp = reinterpret_cast<const uint4*>(prm.x + (size_t)row0 * DM) + lane;
#pragma unroll
        for (int c = 0; c < 4; ++c) gw[c] = __ldg(reinterpret_cast<const uint4*>(prm.gate_w) + c * 32 + lane);
        float mine = 0.f;
#pragma unroll 1
        for (int rb = 0; rb < 8; rb += 2) {
          uint4 xv[2][4];
#pragma unroll
          for (int r = 0; r < 2; ++r)
#pragma unroll
            for (int c = 0; c < 4; ++c) xv[r][c] = __ldg(xp + r * 128 + c * 32);
          xp += 256;
#pragma unroll
          for (int r = 0; r < 2; ++r) {
            float s = 0.f;
#pragma unroll
            for (int c = 0; c < 4; ++c) {
              const uint32_t xa[4] = {xv[r][c].x, xv[r][c].y, xv[r][c].z, xv[r][c].w};
              const uint32_t ga[4] = {gw[c].x, gw[c].y, gw[c].z, gw[c].w};
#pragma unroll
              for (int e = 0; e < 4; ++e) {
                const uint32_t pr = mul_bf16x2(xa[e], ga[e]);
                s += bf_lo(pr);
                s += bf_hi(pr);
              }
            }
#pragma unroll
            for (int o = 16; o > 0; o >>= 1) s += __shfl_xor_sync(0xffffffffu, s, o);
            if (lane == rb + r) mine = s;
          }
        }
        if (lane < 8) g_gate[row0 + lane] = round_bf16(1.f / (1.f + expf(-round_bf16(mine))));
        __syncwarp();
        if (lane == 0) red_release_add(&g_flagG[m * 64], 1);
      }
      const uint64_t tre = reinterpret_cast<uint64_t>(Hm) + (size_t)(KB_S + 4 * j + blk) * A_BYTES;
      unsigned* aggflag = &g_flagAgg[(j * 2 + blk) * 64 + lane];
      unsigned* doneflag = &g_flagH[m * 64 + 16 + j];
      const float4* agg = g_agg + (j * 2 + blk) * 32 + lane;
      const uint32_t zero = prm.zero;
      const uint32_t ring = sbase + SM_STG + (2 + blk) * 8192, rbar = bars + 8 * (BAR_SCANLD + 4 * blk);
      const int urow = (m * NKB + KB_S + 4 * j + blk) * 128;
      auto fetch = [&](uint32_t g) {
        if (elect_one()) {
          mbar_expect_tx(rbar + 8 * (g & 3), 2048);
          tma_3d(ring + (g & 3) * 2048, &tm_u, 0, urow + (g & 15) * 8, 0, rbar + 8 * (g & 3));
        }
      };
      float sr[2] = {0.f, 0.f}, si[2] = {0.f, 0.f};
      uint64_t pout = tre + lane * 4;
      auto group = [&](uint32_t g, bool out) {
        mbar_wait(rbar + 8 * (g & 3), (g >> 2) & 1);
        const uint32_t a = ring + (g & 3) * 2048 + lane * 4;
        uint32_t ur[8], ui[8];
#pragma unroll
        for (int t = 0; t < 8; ++t) { ur[t] = lds32(a + t * 128); ui[t] = lds32(a + t * 128 + 1024); }
#pragma unroll
        for (int t = 0; t < 8; ++t) {
          const uint32_t z0 = __float_as_uint(si[1]) & zero;
          const float ar = bf_lo_dep(ur[t], z0), ai = bf_lo_dep(ui[t], z0);
          if (out) cmad(sr[0], si[0], lr[0], -li[0], fmaf(-ai, ci[0], ar * cr[0]), fmaf(-ar, ci[0], -ai * cr[0]));
          else cmad(sr[0], si[0], lr[0], li[0], ar, ai);
          const uint32_t z1 = __float_as_uint(si[0]) & zero;
          const float br = bf_hi_dep(ur[t], z1), bi = bf_hi_dep(ui[t], z1);
          if (out) cmad(sr[1], si[1], lr[1], -li[1], fmaf(-bi, ci[1], br * cr[1]), fmaf(-br, ci[1], -bi * cr[1]));
          else cmad(sr[1], si[1], lr[1], li[1], br, bi);
          if (out) {
            asm volatile("st.global.b32 [%0], %1;" ::"l"(pout + t * 128), "r"(pack_bf16(sr[0], sr[1])) : "memory");
            asm volatile("st.global.b32 [%0], %1;" ::"l"(pout + t * 128 + 2 * A_BYTES), "r"(pack_bf16(si[0], si[1])) : "memory");
          }
        }
        __syncwarp();
        if (g < 28) fetch(g + 4);
      };
      mbar_wait(bars + 8 * BAR_USTORED, 0);
#pragma unroll 1
      for (uint32_t g = 0; g < 4; ++g) fetch(g);
#pragma unroll 1
      for (uint32_t g = 0; g < 16; ++g) group(g, false);
      asm volatile("st.global.v4.f32 [%0], {%1, %2, %3, %4};" ::"l"(add32(agg, m * 8192)), "f"(sr[0]), "f"(si[0]), "f"(sr[1]), "f"(si[1]) : "memory");
      __syncwarp();
      if (lane == m) st_release(aggflag, ep + 1);
      if (lane < m) wait_flag(aggflag, ep + 1);
      __syncwarp();
      sr[0] = si[0] = sr[1] = si[1] = 0.f;
#pragma unroll 1
      for (int mp = 0; mp < m; mp += 8) {
        float4 a[8];
#pragma unroll
        for (int i = 0; i < 8; ++i) if (mp + i < m) a[i] = __ldcg(agg + i * 512);
        agg += 4096;
#pragma unroll
        for (int i = 0; i < 8; ++i)
          if (mp + i < m) {
            cmad(sr[0], si[0], pr[0], pi[0], a[i].x, a[i].y);
            cmad(sr[1], si[1], pr[1], pi[1], a[i].z, a[i].w);
          }
      }
      cmad(sr[0], si[0], cr[0], ci[0], 0.f, 0.f);
      cmad(sr[1], si[1], cr[1], ci[1], 0.f, 0.f);
      si[0] = -si[0]; si[1] = -si[1];
#pragma unroll 1
      for (uint32_t g = 16; g < 32; ++g, pout += 1024) group(g, true);
      fence_proxy_async();
      __syncwarp();
      if (lane == 0) { mbar_arrive(bars + 8 * BAR_SCANDONE); red_release_add(doneflag, 1); }
      if (blk == 0) {
        mbar_wait(bars + 8 * BAR_SCANDONE, 0);
        if (elect_one()) {
          mbar_expect_tx(bars + 8 * BAR_XS1, 16384);
          tma_2d(sbase + SM_STG + 16384, &tm_x, (j ^ 1) * 128 + 64, m * 128, bars + 8 * BAR_XS1);
        }
      }
    }
    if (lane == 0 && warp != 0) {
      const unsigned old = atomicAdd(&g_done, 1);
      if (old == NCTA * 3 - 1) { g_done = 0; atomicAdd(&g_epoch, 1); }
    }
  } else {
    asm volatile("setmaxnreg.inc.sync.aligned.u32 216;");
    const int wg = (warp >> 2) - 1;
    const int row0 = wg * 64 + (warp & 3) * 16;
    const uint32_t ebars = mapa(bars, lane == 0 ? rank : rank ^ 1);
    const uint64_t xin = reinterpret_cast<uint64_t>(prm.out) + (uint32_t)(((m * 128 + row0) * DM + j * 128) * 4 + lane * 16);
    const uint32_t stg0 = sbase + SM_STG + ((warp & 3) * 16 + (lane & 15)) * 128 + (((lane >> 4) ^ (lane & 7)) << 4);
    float acc[128];
    uint32_t pk[64];
    int part = 0, nparts = 0;
    uint32_t fbar = 0, sbar = 0, dst = 0, dinc = 0;
    auto flush = [&](bool block) {
      if (fbar) {
        if (block) mbar_wait(fbar, 0);
        else if (!__all_sync(0xffffffffu, mbar_test(fbar, 0))) return;
      }
#pragma unroll
      for (int p = 0; p < 4; ++p)
        if (part == p) {
#pragma unroll
          for (int i = 4 * p; i < 4 * p + 4; ++i)
            stmatrix_x4(dst ^ ((i & 3) << 5), pk[4 * i], pk[4 * i + 1], pk[4 * i + 2], pk[4 * i + 3]);
        }
      __syncwarp();
      if (lane == 0) mbar_arrive(sbar);
      fbar = dinc ? (fbar ? fbar + 8 : 0) : sbar + 8 * (BAR_STGFREE - BAR_STGFULL);
      sbar += 8; dst += dinc; ++part;
    };
    const uint32_t da0 = desc_k(sbase + wg * 8192);
    uint32_t stage = 0, fph = 0;
    uint32_t lagph = 0;
    uint32_t rel = 0;
    auto steps = [&](auto mode_c, int it0, int it1, int nsteps, auto&& hook) {
      constexpr bool FLUSH = decltype(mode_c)::value == 1 || decltype(mode_c)::value == 2;
      constexpr int MODE = decltype(mode_c)::value == 3 ? 1 : decltype(mode_c)::value;
      constexpr uint32_t O1 = MODE == 0 ? 2 : 128, O2 = MODE == 0 ? 4 : MODE == 1 ? 1024 : 768, O3 = MODE == 0 ? 6 : O2 + 128;
      const uint32_t db0 = MODE == 0 ? desc_k(sbase + A_BYTES) : desc_mn4k(sbase + A_BYTES);
      auto mma = [&](uint32_t da, uint32_t db, int sc) {
        if (MODE == 0) wgmma_n256_kmaj(acc, D(da), D(db), sc);
        if (MODE == 1) wgmma_n256_nmaj(acc, D(da), D(db), sc);
        if (MODE == 2) wgmma_n192_nmaj(acc, D(da), D(db), sc);
      };
#pragma unroll 1
      for (int it = it0; it < it1; ++it) {
        if (it == nsteps - 1 && wg == 1) mbar_wait(bars + 8 * BAR_LAG, lagph);
        mbar_wait(bars + 8 * (BAR_FULL1 + stage), fph);
        const uint32_t so = stage * (ST1_BYTES >> 4);
        wgmma_fence();
        mma(da0 + so, db0 + so, it);
        mma(da0 + so + 2, db0 + so + O1, 1);
        wgmma_commit();
        wgmma_wait<1>();
        if (rel != 0 && lane < 2) mbar_arrive_cl(ebars + rel);
        rel = 8 * (BAR_EMPTY1 + stage);
        if (FLUSH && part < nparts && (dinc != 0 || ((it ^ wg) & 1) == 0 || it >= 12)) flush(it >= 12);
        hook(it);
        wgmma_fence();
        mma(da0 + so + 4, db0 + so + O2, 1);
        mma(da0 + so + 6, db0 + so + O3, 1);
        wgmma_commit();
        if (it == nsteps - 1 && wg == 0 && lane == 0) mbar_arrive(bars + 8 * BAR_LAG);
        stage = (stage + 1) & 3;
        fph ^= (stage == 0);
      }
    };
    auto tile_end = [&]() {
      wgmma_wait<0>();
      if (lane < 2) mbar_arrive_cl(ebars + 8 * (BAR_EMPTY1 + 3));
      rel = 0;
      lagph ^= 1;
    };
    auto nohook = [](int) {};
    steps(std::integral_constant<int, 0>{}, 0, 16, 16, nohook);
    tile_end();
#pragma unroll
    for (int i = 0; i < 64; ++i) asm volatile("cvt.rn.bf16x2.f32 %0, %1, %2;" : "=r"(pk[i]) : "f"(acc[2 * i + 1]), "f"(acc[2 * i]));
    part = 0; nparts = 4; sbar = bars + 8 * (BAR_STGFULL + 4 * wg);
    fbar = wg ? bars + 8 * BAR_STGFREE : 0; dst = stg0; dinc = 8192;
    steps(std::integral_constant<int, 1>{}, 0, 16, 16, nohook);
    tile_end();
#pragma unroll
    for (int i = 0; i < 64; ++i) asm volatile("cvt.rn.relu.bf16x2.f32 %0, %1, %2;" : "=r"(pk[i]) : "f"(acc[2 * i + 1]), "f"(acc[2 * i]));
    part = 0; sbar = bars + 8 * (BAR_STGFULL + 8 + 4 * wg);
    fbar = bars + 8 * (BAR_STGFREE + 4 + wg); dst = stg0 + wg * 8192; dinc = 0;
    steps(std::integral_constant<int, 2>{}, 0, 16, 16, nohook);
    tile_end();
#pragma unroll
    for (int i = 0; i < 48; ++i) asm volatile("cvt.rn.relu.bf16x2.f32 %0, %1, %2;" : "=r"(pk[i]) : "f"(acc[2 * i + 1]), "f"(acc[2 * i]));
    part = 0; nparts = 3; sbar = bars + 8 * (BAR_STGFULL + 16 + 4 * wg);
    steps(std::integral_constant<int, 1>{}, 0, SKIPAT, 28, nohook);
    mbar_wait(bars + 8 * BAR_G, 0);
    const float g0 = s_g[row0 + (lane >> 2)], g1 = s_g[row0 + (lane >> 2) + 8];
    const float og0 = round_bf16(1.f - g0), og1 = round_bf16(1.f - g1);
    steps(std::integral_constant<int, 3>{}, SKIPAT, 28, 28, [&](int it) {
#pragma unroll
      for (int pc = 0; pc < 2; ++pc)
        if (it == (pc ? SKIP2 : SKIPAT) + 1 - wg) {
          mbar_wait(bars + 8 * (pc ? BAR_XS1 : BAR_XS), 0);
#pragma unroll
          for (int h = 2 * pc; h < 2 * pc + 2; ++h) {
            uint32_t xs[8], dk[4];
#pragma unroll
            for (int c = 0; c < 2; ++c)
              asm volatile("ldmatrix.sync.aligned.m8n8.x4.shared.b16 {%0, %1, %2, %3}, [%4];"
                           : "=r"(xs[4 * c]), "=r"(xs[4 * c + 1]), "=r"(xs[4 * c + 2]), "=r"(xs[4 * c + 3])
                           : "r"(((stg0 + wg * 8192) ^ (((2 * h + c) & 3) << 5)) + pc * 16384) : "memory");
#pragma unroll
            for (int c = 0; c < 4; ++c) dk[c] = lds32(sbase + SM_G + 512 + (4 * h + c) * 16 + (lane & 3) * 4);
#pragma unroll
            for (int e = 0; e < 8; ++e) {
              const uint32_t p = mul_bf16x2(xs[e], dk[e >> 1]);
              const float g = (e & 1) ? g1 : g0;
              pk[16 * h + 2 * e] = __float_as_uint(g * bf_lo(p));
              pk[16 * h + 2 * e + 1] = __float_as_uint(g * bf_hi(p));
            }
          }
          __syncwarp();
          if (pc == 1 && lane < 2) mbar_arrive_cl(ebars + 8 * BAR_STGDEAD);
        }
    });
    tile_end();

#pragma unroll
    for (int i = 0; i < 64; ++i) asm volatile("fma.rn.f32 %0, %1, %2, %0;" : "+r"(pk[i]) : "f"((i & 2) ? og1 : og0), "f"(acc[i]));
    const uint32_t db2 = desc_k(sbase + A_BYTES);
    const uint64_t xout = xin + (int64_t)(kh ? -512 : 512);
    uint32_t slot = 0, ph = 0;
    auto g2_step = [&](int idx, auto&& hook) {
      mbar_wait(bars + 8 * (BAR_FULL2 + slot), ph);
      const uint32_t so = slot * (ST2_BYTES >> 4);
      wgmma_fence();
      wgmma_n128_kmaj(acc, D(da0 + so), D(db2 + so), idx);
      wgmma_n128_kmaj(acc, D(da0 + so + 2), D(db2 + so + 2), 1);
      wgmma_commit();
      wgmma_wait<1>();
      if (rel != 0 && lane < 2) mbar_arrive_cl(ebars + rel);
      rel = 8 * (BAR_EMPTY2 + slot);
      hook();
      wgmma_fence();
      wgmma_n128_kmaj(acc, D(da0 + so + 4), D(db2 + so + 4), 1);
      wgmma_n128_kmaj(acc, D(da0 + so + 6), D(db2 + so + 6), 1);
      wgmma_commit();
      if (++slot == NST2) { slot = 0; ph ^= 1; }
    };
    constexpr int TAIL0 = 32 - NST2 + 1;
#pragma unroll
    for (int it = 0; it < XSEND; ++it)
      g2_step(it + prm.zero, [&]() {
#pragma unroll
        for (int c = it * 16 / XSEND; c < (it + 1) * 16 / XSEND; ++c)
          asm volatile("st.global.v4.b32 [%0], {%1, %2, %3, %4};" ::"l"(xout + c * 4096),
                       "r"(pk[4 * c]), "r"(pk[4 * c + 1]), "r"(pk[4 * c + 2]), "r"(pk[4 * c + 3]) : "memory");
      });
    __syncwarp();
    if (lane == 0) mbar_arrive(bars + 8 * BAR_XSENT);
#pragma unroll 1
    for (int it = XSEND; it < TAIL0; ++it) g2_step(it, [&]() {});
    auto recv = [&](int c0, int c1) {
#pragma unroll
      for (int c = c0; c < c1; ++c)
        asm volatile("ld.global.cg.v4.b32 {%0, %1, %2, %3}, [%4];" : "=r"(pk[4 * c]), "=r"(pk[4 * c + 1]), "=r"(pk[4 * c + 2]), "=r"(pk[4 * c + 3])
                     : "l"(xin + c * 4096) : "memory");
    };
    if (wg == 1) {
      wgmma_wait<0>();
      if (lane == 0) mbar_arrive(bars + 8 * BAR_OFREE);
      mbar_wait(bars + 8 * BAR_LAST, 0);
    }
#pragma unroll
    for (int it = TAIL0; it < 32; ++it) {
      mbar_wait(bars + 8 * (BAR_FULL2 + it % NST2), (it / NST2) & 1);
      const uint32_t so = (it % NST2) * (ST2_BYTES >> 4);
      wgmma_fence();
      wgmma_n128_kmaj(acc, D(da0 + so), D(db2 + so), 1);
      wgmma_n128_kmaj(acc, D(da0 + so + 2), D(db2 + so + 2), 1);
      wgmma_n128_kmaj(acc, D(da0 + so + 4), D(db2 + so + 4), 1);
      wgmma_n128_kmaj(acc, D(da0 + so + 6), D(db2 + so + 6), 1);
      wgmma_commit();
      if (it == TAIL0 + 1) { mbar_wait(bars + 8 * BAR_XREADY, 0); recv(0, 8); }
      if (it == TAIL0 + 2) recv(8, 16);
    }
    const uint32_t obuf = sbase + (4 + wg) * ST2_BYTES + (warp & 3) * 8192;
    wgmma_wait<1>();
    if (lane == 0) mbar_arrive(bars + 8 * (wg ? BAR_LAST1 : BAR_LAST));
    if (wg == 0) mbar_wait(bars + 8 * BAR_OFREE, 0);
    mbar_wait(bars + 8 * (wg ? BAR_LAST1 : BAR_LAST), 0);
    wgmma_wait<0>();
    {
      const int q = lane & 3, r = lane >> 2;
      const uint32_t o0 = obuf + r * 128 + (((q >> 1) ^ r) << 4) + (q & 1) * 8;
#pragma unroll
      for (int cb = 0; cb < 4; ++cb) {
#pragma unroll
        for (int a = 0; a < 4; ++a) {
          const int i = 4 * (4 * cb + a);
          const uint32_t p = (o0 ^ (a << 5)) + cb * 2048;
          asm volatile("st.shared.v2.f32 [%0], {%1, %2};" ::"r"(p), "f"(fmaf(g0, acc[i], fmaf(og0, acc[64 + i], __uint_as_float(pk[i])))),
                       "f"(fmaf(g0, acc[i + 1], fmaf(og0, acc[64 + i + 1], __uint_as_float(pk[i + 1])))) : "memory");
          asm volatile("st.shared.v2.f32 [%0+1024], {%1, %2};" ::"r"(p), "f"(fmaf(g1, acc[i + 2], fmaf(og1, acc[64 + i + 2], __uint_as_float(pk[i + 2])))),
                       "f"(fmaf(g1, acc[i + 3], fmaf(og1, acc[64 + i + 3], __uint_as_float(pk[i + 3])))) : "memory");
        }
        asm volatile("fence.proxy.async.shared::cta;" ::: "memory");
        if (cb == 0) fence_proxy_async();
        __syncwarp();
        if (lane == 0) tma_store_2d(&tm_out, obuf + cb * 2048, j * 128 + cb * 32, m * 128 + row0);
      }
      if (lane == 0) asm volatile("cp.async.bulk.commit_group;\ncp.async.bulk.wait_group.read 0;" ::: "memory");
    }
  }
}

__global__ void topology_probe() {}

typedef CUresult (*EncodeFn)(CUtensorMap*, CUtensorMapDataType, cuuint32_t, void*, const cuuint64_t*, const cuuint64_t*,
                             const cuuint32_t*, const cuuint32_t*, CUtensorMapInterleave, CUtensorMapSwizzle,
                             CUtensorMapL2promotion, CUtensorMapFloatOOBfill);

void make_map(EncodeFn fn, CUtensorMap* map, CUtensorMapDataType dt, const void* ptr, int rank, const cuuint64_t* dims,
              const cuuint64_t* strides, const cuuint32_t* box, CUtensorMapSwizzle sw = CU_TENSOR_MAP_SWIZZLE_128B) {
  const cuuint32_t es[5] = {1, 1, 1, 1, 1};
  fn(map, dt, rank, const_cast<void*>(ptr), dims, strides, box, es, CU_TENSOR_MAP_INTERLEAVE_NONE,
     sw, CU_TENSOR_MAP_L2_PROMOTION_L2_128B, CU_TENSOR_MAP_FLOAT_OOB_FILL_NONE);
}

}

extern "C" void kernel_launch(void* const* d_in, const int* in_sizes, int n_in, void* d_out, int out_size) {
  (void)in_sizes; (void)n_in; (void)out_size;
  static EncodeFn encode = nullptr;
  static bool known_topology = false;
  if (!encode) {
    void* fn = nullptr;
    cudaDriverEntryPointQueryResult qr;
    cudaGetDriverEntryPoint("cuTensorMapEncodeTiled", &fn, cudaEnableDefault, &qr);
    encode = reinterpret_cast<EncodeFn>(fn);
    cudaFuncSetAttribute(fused_kernel<true>, cudaFuncAttributeMaxDynamicSharedMemorySize, SMEM_BYTES);
    cudaFuncSetAttribute(fused_kernel<false>, cudaFuncAttributeMaxDynamicSharedMemorySize, SMEM_BYTES);
    cudaFuncSetAttribute(topology_probe, cudaFuncAttributeMaxDynamicSharedMemorySize, SMEM_BYTES);
    int sig[3] = {0, 0, 0};
    for (int i = 0; i < 3; ++i) {
      cudaLaunchConfig_t cfg = {};
      cfg.gridDim = dim3(NCTA); cfg.blockDim = dim3(NTHREADS); cfg.dynamicSmemBytes = SMEM_BYTES;
      cudaLaunchAttribute at[1];
      at[0].id = cudaLaunchAttributeClusterDimension;
      at[0].val.clusterDim.x = 2 << i; at[0].val.clusterDim.y = 1; at[0].val.clusterDim.z = 1;
      cfg.attrs = at; cfg.numAttrs = 1;
      if (cudaOccupancyMaxActiveClusters(&sig[i], topology_probe, &cfg) != cudaSuccess) (void)cudaGetLastError();
    }
    known_topology = sig[0] == 66 && sig[1] == 30 && sig[2] == 15;
  }
  const CUtensorMapDataType BF = CU_TENSOR_MAP_DATA_TYPE_BFLOAT16;
  CUtensorMap tx, tbre, tbim, tw1a, tw1b, tw2, tcre, tcim, tout, thld, thst, tu;
  {
    const cuuint64_t dims[2] = {DM, SEQ}, st[1] = {DM * 2};
    const cuuint32_t box[2] = {64, 128};
    make_map(encode, &tx, BF, d_in[0], 2, dims, st, box);
  }
  {
    const cuuint64_t dims[2] = {DM, PCH}, st[1] = {DM * 2};
    const cuuint32_t box[2] = {64, 128};
    make_map(encode, &tbre, BF, d_in[3], 2, dims, st, box);
    make_map(encode, &tbim, BF, d_in[4], 2, dims, st, box);
    const cuuint32_t boxc[2] = {64, 64};
    make_map(encode, &tcre, BF, d_in[5], 2, dims, st, boxc);
    make_map(encode, &tcim, BF, d_in[6], 2, dims, st, boxc);
  }
  {
    const cuuint64_t dims[3] = {64, DM, DFF / 64}, st[2] = {DFF * 2, 128};
    const cuuint32_t boxa[3] = {64, 32, 4}, boxb[3] = {64, 32, 3};
    make_map(encode, &tw1a, BF, d_in[10], 3, dims, st, boxa);
    make_map(encode, &tw1b, BF, d_in[10], 3, dims, st, boxb);
  }
  {
    const cuuint64_t dims[3] = {64, DFF, DM / 64}, st[2] = {DM * 2, 128};
    const cuuint32_t box[3] = {64, 32, 2};
    make_map(encode, &tw2, BF, d_in[11], 3, dims, st, box);
  }
  {
    const cuuint64_t dims[2] = {DM, SEQ}, st[1] = {DM * 4};
    const cuuint32_t box[2] = {32, 16};
    make_map(encode, &tout, CU_TENSOR_MAP_DATA_TYPE_FLOAT32, d_out, 2, dims, st, box);
  }
  {
    void* hptr = nullptr;
    cudaGetSymbolAddress(&hptr, g_H);
    const cuuint64_t dims[2] = {64, 16 * NKB * 128}, st[1] = {128};
    const cuuint32_t boxl[2] = {64, 128}, boxs[2] = {64, 32};
    make_map(encode, &thld, BF, hptr, 2, dims, st, boxl);
    make_map(encode, &thst, BF, hptr, 2, dims, st, boxs);
    const cuuint64_t dimu[3] = {64, 16 * NKB * 128 - 256, 2}, stu[2] = {128, 2 * A_BYTES};
    const cuuint32_t boxu[3] = {64, 8, 2};
    make_map(encode, &tu, BF, hptr, 3, dimu, stu, boxu, CU_TENSOR_MAP_SWIZZLE_NONE);
  }
  Params prm;
  prm.x = (const __nv_bfloat16*)d_in[0];
  prm.lam_re = (const __nv_bfloat16*)d_in[1];
  prm.lam_im = (const __nv_bfloat16*)d_in[2];
  prm.log_dt = (const __nv_bfloat16*)d_in[7];
  prm.dskip = (const __nv_bfloat16*)d_in[8];
  prm.gate_w = (const __nv_bfloat16*)d_in[12];
  prm.out = (float*)d_out;
  prm.zero = 0;
  if (known_topology) fused_kernel<true><<<NCTA, NTHREADS, SMEM_BYTES>>>(tx, tbre, tbim, tw1a, tw1b, tw2, tcre, tcim, tout, thld, thst, tu, prm);
  else fused_kernel<false><<<NCTA, NTHREADS, SMEM_BYTES>>>(tx, tbre, tbim, tw1a, tw1b, tw2, tcre, tcim, tout, thld, thst, tu, prm);
}
```
